```python
import torch

def _softmax(x, axis=-1):
    return torch.softmax(x, dim=axis)
def _gelu(x):
    return torch.nn.functional.gelu(x, approximate="tanh")
def _silu(x):
    return torch.nn.functional.silu(x)
def _sigmoid(x):
    return torch.sigmoid(x)
def _layernorm(x, axis=-1, eps=1e-5):
    m = x.mean(dim=axis, keepdim=True)
    v = x.var(dim=axis, keepdim=True, unbiased=False)
    return (x - m) / torch.sqrt(v + eps)
def _scatter_add(tgt, idx, src, axis=0):
    return tgt.clone().index_add_(axis, idx, src)
def _segment_sum(src, seg, n):
    out = torch.zeros((n,) + src.shape[1:], dtype=src.dtype)
    return out.index_add_(0, seg, src)
def _pad(x, pw):
    flat = tuple(v for pair in reversed(pw) for v in pair)
    return torch.nn.functional.pad(x, flat)

kernel_name = 'standalone__normalfloat_lut_af4__prompt'

def setup_inputs():

    _w = (lambda a: (lambda t: t.to(torch.bfloat16) if t.is_floating_point() else t)(torch.as_tensor(a)))
    B, S, D, F = 1, 2048, 576, 4608
    G = 32 if 32 > 0 else D
    D = (D // G) * G
    ng = D // G
    nf4 = torch.tensor([
        -1.0, -0.6961928009986877, -0.5250730514526367, -0.39491748809814453,
        -0.28444138169288635, -0.18477343022823334, -0.09105003625154495, 0.0,
        0.07958029955625534, 0.16093020141124725, 0.24611230194568634,
        0.33791524171829224, 0.44070982933044434, 0.5626170039176941,
        0.7229568362236023, 1.0,
    ], dtype=float)
    qw = torch.randint(0, 16, (D, F)).to(torch.int64)
    return {
        "x": _w((lambda *s: torch.randn(*s, dtype=torch.bfloat16) * 0.05)(B, S, D)),
        "qw": _w(qw),
        "lut": _w(nf4),
        "scales": _w(torch.abs((lambda *s: torch.randn(*s, dtype=torch.bfloat16) * 0.05)(ng, F)).to(float) + 0.01),
    }

def reference(x, qw, lut, scales):
    B, S, D = x.shape
    ng, F = scales.shape
    G = D // ng
    deq = lut[qw]
    s = (lambda x, n, axis: torch.repeat_interleave(x, n, dim=axis))(scales, G, axis=0)
    w = (lambda x, dt: x.to(dt))(deq, x.dtype) * (lambda x, dt: x.to(dt))(s, x.dtype)
    return torch.einsum("bsd,df->bsf", x, w)
```

```cpp
#include <cuda_runtime.h>
#include <cuda_bf16.h>
#include <cuda.h>
#include <stdint.h>

namespace {
constexpr int S_ = 2048, D_ = 576, F_ = 4608;
constexpr int BN = 144, NCH = 9;
constexpr int HC = BN * 64;
constexpr int XS = 8192;
constexpr int OFF_X = 2 * NCH * HC;
constexpr int OFF_STG = OFF_X + 6 * XS;
constexpr int OFF_BAR = OFF_X + 8 * XS;
constexpr int OFF_FULL = OFF_BAR, OFF_EMPTY = OFF_BAR + 64;
constexpr int OFF_STAGED = OFF_BAR + 128, OFF_FREE = OFF_BAR + 208;
constexpr int OFF_DONE = OFF_BAR + 192, OFF_IDLE = OFF_BAR + 200;
constexpr int OFF_WFULL = OFF_BAR + 464;
constexpr int SMEM_BYTES = OFF_BAR + 1024;
constexpr int NPW = 7;
constexpr int NUNIT = 9 * NCH;

struct Knobs { int unit0, unit_step, unit_gap, x0, x1; };
constexpr Knobs kn = {450, 200, 200, 650, 2150};

__device__ __forceinline__ uint32_t smem_u32(const void* p) { return (uint32_t)__cvta_generic_to_shared(p); }
__device__ __forceinline__ bool elect() { uint32_t p; asm volatile("{\n.reg .pred p;\nelect.sync _|p, 0xffffffff;\nselp.u32 %0, 1, 0, p;\n}" : "=r"(p)); return p; }
__device__ __forceinline__ void mbar_init(uint32_t bar, uint32_t cnt) { asm volatile("mbarrier.init.shared::cta.b64 [%0], %1;" :: "r"(bar), "r"(cnt) : "memory"); }
__device__ __forceinline__ void mbar_expect_tx(uint32_t bar, uint32_t bytes) { asm volatile("mbarrier.arrive.expect_tx.shared::cta.b64 _, [%0], %1;" :: "r"(bar), "r"(bytes) : "memory"); }
__device__ __forceinline__ void mbar_arrive(uint32_t bar) { asm volatile("mbarrier.arrive.shared::cta.b64 _, [%0];" :: "r"(bar) : "memory"); }
__device__ __forceinline__ void mbar_wait(uint32_t bar, uint32_t parity) {
    asm volatile("{\n.reg .pred p;\n.reg .u32 n;\n"
                 "mbarrier.try_wait.parity.shared::cta.b64 p, [%0], %1;\n@p bra.uni LAB_DONE;\nmov.u32 n, 0;\n"
                 "LAB_WAIT:\nmbarrier.try_wait.parity.shared::cta.b64 p, [%0], %1;\n@p bra.uni LAB_DONE;\n"
                 "add.u32 n, n, 1;\nsetp.lt.u32 p, n, 0x200000;\n@p bra.uni LAB_WAIT;\ntrap;\nLAB_DONE:\n}"
                 :: "r"(bar), "r"(parity) : "memory");
}
__device__ __forceinline__ uint32_t mbar_test(uint32_t bar, uint32_t parity) {
    uint32_t ok; asm volatile("{\n.reg .pred p;\nmbarrier.test_wait.parity.shared::cta.b64 p, [%1], %2;\nselp.u32 %0, 1, 0, p;\n}" : "=r"(ok) : "r"(bar), "r"(parity) : "memory");
    return ok;
}
__device__ __forceinline__ void tma2d(uint32_t dst, const CUtensorMap* tm, int c0, int c1, uint32_t bar) {
    asm volatile("cp.async.bulk.tensor.2d.shared::cluster.global.mbarrier::complete_tx::bytes [%0], [%1, {%3, %4}], [%2];"
                 :: "r"(dst), "l"(tm), "r"(bar), "r"(c0), "r"(c1) : "memory");
}
__device__ __forceinline__ void bulk_s2s(uint32_t dst, uint32_t src, uint32_t bytes, uint32_t bar) {
    asm volatile("cp.async.bulk.shared::cluster.shared::cta.mbarrier::complete_tx::bytes [%0], [%1], %2, [%3];" :: "r"(dst), "r"(src), "r"(bytes), "r"(bar) : "memory");
}
__device__ __forceinline__ void proxy_fence() { asm volatile("fence.proxy.async.shared::cta;" ::: "memory"); }
__device__ __forceinline__ void init_fence() { asm volatile("fence.mbarrier_init.release.cluster;" ::: "memory"); }
__device__ __forceinline__ void wg_fence() { asm volatile("wgmma.fence.sync.aligned;" ::: "memory"); }
__device__ __forceinline__ void wg_commit() { asm volatile("wgmma.commit_group.sync.aligned;" ::: "memory"); }
template <int N> __device__ __forceinline__ void wg_wait() { asm volatile("wgmma.wait_group.sync.aligned %0;" :: "n"(N) : "memory"); }
__device__ __forceinline__ void bar_sync(int id, int n) { asm volatile("bar.sync %0, %1;" :: "r"(id), "r"(n) : "memory"); }
__device__ __forceinline__ void bar_arrive(int id, int n) { asm volatile("bar.arrive %0, %1;" :: "r"(id), "r"(n) : "memory"); }
__device__ __forceinline__ void cluster_arrive() { asm volatile("barrier.cluster.arrive.relaxed.aligned;" ::: "memory"); }
__device__ __forceinline__ void cluster_wait() { asm volatile("barrier.cluster.wait.aligned;" ::: "memory"); }
__device__ __forceinline__ void wait_until(unsigned t0, unsigned dt) { unsigned now; do { asm volatile("mov.u32 %0, %%clock;" : "=r"(now)); } while (now - t0 < dt); }
__device__ __forceinline__ void sts128(uint32_t a, uint32_t v0, uint32_t v1, uint32_t v2, uint32_t v3) {
    asm volatile("st.shared.v4.u32 [%0], {%1, %2, %3, %4};" :: "r"(a), "r"(v0), "r"(v1), "r"(v2), "r"(v3) : "memory");
}

template <bool B> struct Bool { static constexpr bool value = B; };

constexpr uint32_t DESC_A = (1024u >> 4) | (1u << 30);
constexpr uint32_t DESC_B = (512u >> 4) | (2u << 30);
__device__ __forceinline__ uint64_t mk_desc(uint32_t lo, uint32_t hi) { uint64_t d; asm("mov.b64 %0, {%1, %2};" : "=l"(d) : "r"(lo), "r"(hi)); return d; }
#define ACC_REGS "%0, %1, %2, %3, %4, %5, %6, %7, %8, %9, %10, %11, %12, %13, %14, %15, %16, %17, %18, %19, %20, %21, %22, %23, " \
    "%24, %25, %26, %27, %28, %29, %30, %31, %32, %33, %34, %35, %36, %37, %38, %39, %40, %41, %42, %43, %44, %45, %46, %47, " \
    "%48, %49, %50, %51, %52, %53, %54, %55, %56, %57, %58, %59, %60, %61, %62, %63, %64, %65, %66, %67, %68, %69, %70, %71"
#define A8(d, o) "+f"(d[o]), "+f"(d[o + 1]), "+f"(d[o + 2]), "+f"(d[o + 3]), "+f"(d[o + 4]), "+f"(d[o + 5]), "+f"(d[o + 6]), "+f"(d[o + 7])
__device__ __forceinline__ void wgmma_n144(float (&d)[72], uint32_t a_lo, uint32_t b_lo, int scale_d) {
    asm volatile("{\n.reg .pred p;\nsetp.ne.b32 p, %74, 0;\n"
                 "wgmma.mma_async.sync.aligned.m64n144k16.f32.bf16.bf16 {" ACC_REGS "}, %72, %73, p, 1, 1, 0, 0;\n}\n"
                 : A8(d, 0), A8(d, 8), A8(d, 16), A8(d, 24), A8(d, 32), A8(d, 40), A8(d, 48), A8(d, 56), A8(d, 64)
                 : "l"(mk_desc(a_lo, DESC_A)), "l"(mk_desc(b_lo, DESC_B)), "r"(scale_d));
}
#define O8(d, o) "=f"(d[o]), "=f"(d[o + 1]), "=f"(d[o + 2]), "=f"(d[o + 3]), "=f"(d[o + 4]), "=f"(d[o + 5]), "=f"(d[o + 6]), "=f"(d[o + 7])
__device__ __forceinline__ void wgmma_n144_first(float (&d)[72], uint32_t a_lo, uint32_t b_lo) {
    asm volatile("wgmma.mma_async.sync.aligned.m64n144k16.f32.bf16.bf16 {" ACC_REGS "}, %72, %73, 0, 1, 1, 0, 0;\n"
                 : O8(d, 0), O8(d, 8), O8(d, 16), O8(d, 24), O8(d, 32), O8(d, 40), O8(d, 48), O8(d, 56), O8(d, 64)
                 : "l"(mk_desc(a_lo, DESC_A)), "l"(mk_desc(b_lo, DESC_B)));
}
__device__ __forceinline__ void acc_fence(float (&d)[72]) {
#pragma unroll
    for (int i = 0; i < 72; i++) asm volatile("" : "+f"(d[i]) :: "memory");
}
template <bool FIRST = false>
__device__ __forceinline__ void mma_half(float (&d)[72], uint32_t a_lo, uint32_t b_lo) {
    wg_fence();
    if (FIRST) wgmma_n144_first(d, a_lo, b_lo); else wgmma_n144(d, a_lo, b_lo, 1);
    wgmma_n144(d, a_lo + 2, b_lo + 2, 1);
    wg_commit();
}
__device__ __forceinline__ void mma_step(float (&d)[72], uint32_t a_lo, uint32_t b_lo, int accumulate) {
    wg_fence();
    wgmma_n144(d, a_lo, b_lo, accumulate);
    wgmma_n144(d, a_lo + 2, b_lo + 2, 1);
    wgmma_n144(d, a_lo + 4, b_lo + (HC >> 4), 1);
    wgmma_n144(d, a_lo + 6, b_lo + (HC >> 4) + 2, 1);
    wg_commit();
}
__device__ __forceinline__ uint32_t pack_bf16(float lo, float hi) {
    uint32_t r; asm("cvt.rn.bf16x2.f32 %0, %1, %2;" : "=r"(r) : "f"(hi), "f"(lo)); return r;
}

__device__ __forceinline__ uint32_t prmt(uint32_t a, uint32_t b, uint32_t c) { uint32_t r; asm("prmt.b32 %0, %1, %2, %3;" : "=r"(r) : "r"(a), "r"(b), "r"(c)); return r; }
__device__ __forceinline__ uint32_t hmul2(uint32_t a, uint32_t b) { uint32_t r; asm("mul.rn.bf16x2 %0, %1, %2;" : "=r"(r) : "r"(a), "r"(b)); return r; }
__device__ __forceinline__ uint32_t unit_kind(uint32_t pos) { return pos == 1 ? 8 : pos - (pos > 1); }
struct Raw { uint4 q[8]; };
struct Lut { uint32_t lo[4], hi[4], idn; };
struct Dq { const char* qw; const char* sc; uint32_t qA, qB, sA, sB, wA, wB; };
__device__ __forceinline__ void dq_load_at(const char* qp, const char* sp, Raw& r, uint2& s) {
#pragma unroll
    for (int i = 0; i < 8; i++)
        asm volatile("ld.global.L1::no_allocate.v4.u32 {%0,%1,%2,%3}, [%4];" : "=r"(r.q[i].x), "=r"(r.q[i].y), "=r"(r.q[i].z), "=r"(r.q[i].w) : "l"(qp + i * (F_ * 4)) : "memory");
    asm volatile("ld.global.v2.u32 {%0,%1}, [%2];" : "=r"(s.x), "=r"(s.y) : "l"(sp) : "memory");
}
__device__ __forceinline__ void dq_load(const Dq& d, uint32_t u, Raw& r, uint2& s) {
    const uint32_t c = (u * 57u) >> 9, j = unit_kind(u - c * 9);
    const uint32_t g = c * 2 + ((j >> 2) & 1), cb = j & 3;
    dq_load_at(d.qw + (g * (32 * F_ * 4) + cb * 128 + (j == 8 ? d.qB : d.qA)), d.sc + (g * (F_ * 2) + cb * 64 + (j == 8 ? d.sB : d.sA)), r, s);
}
__device__ __forceinline__ uint32_t pack4(uint32_t a, uint32_t b, uint32_t c, uint32_t d, uint32_t c16) {
    uint32_t r;
    asm volatile("{\n.reg .u32 t, u;\nmad.lo.u32 t, %2, %5, %1;\nmad.lo.u32 u, %4, %5, %3;\nmad.lo.u32 %0, u, 256, t;\n}" : "=r"(r) : "r"(a), "r"(b), "r"(c), "r"(d), "r"(c16));
    return r;
}
__device__ __forceinline__ void dq_pack(const Raw& r, uint32_t (&sel)[8], uint32_t c16) {
#pragma unroll
    for (int h = 0; h < 2; h++) {
        sel[h * 4 + 0] = pack4(r.q[4 * h].x, r.q[4 * h + 1].x, r.q[4 * h + 2].x, r.q[4 * h + 3].x, c16);
        sel[h * 4 + 1] = pack4(r.q[4 * h].y, r.q[4 * h + 1].y, r.q[4 * h + 2].y, r.q[4 * h + 3].y, c16);
        sel[h * 4 + 2] = pack4(r.q[4 * h].z, r.q[4 * h + 1].z, r.q[4 * h + 2].z, r.q[4 * h + 3].z, c16);
        sel[h * 4 + 3] = pack4(r.q[4 * h].w, r.q[4 * h + 1].w, r.q[4 * h + 2].w, r.q[4 * h + 3].w, c16);
    }
}
__device__ __forceinline__ void dq_quad(const Lut& L, uint32_t sel, uint32_t m7c, uint32_t s2, uint32_t& o0, uint32_t& o1) {
    uint32_t m7 = sel & m7c, pick;
    asm("lop3.b32 %0, %1, 0x4444, %2, 0xea;" : "=r"(pick) : "r"(sel >> 1), "r"(L.idn));
    const uint32_t lo = prmt(prmt(L.lo[0], L.lo[1], m7), prmt(L.lo[2], L.lo[3], m7), pick);
    const uint32_t hi = prmt(prmt(L.hi[0], L.hi[1], m7), prmt(L.hi[2], L.hi[3], m7), pick);
    o0 = hmul2(prmt(lo, hi, 0x5140), s2);
    o1 = hmul2(prmt(lo, hi, 0x7362), s2);
}
__device__ __forceinline__ void dq_store(const Dq& d, const Lut& L, uint32_t u, const uint32_t (&sel)[8], uint2 s, uint32_t m7c,
                                         uint32_t sb, uint32_t pb, bool lead) {
    const uint32_t c = (u * 57u) >> 9, j = unit_kind(u - c * 9);
    const uint32_t base = (c * 2 + ((j >> 2) & 1)) * HC + (j == 8 ? 8192 : (j & 3) * 2048);
    const uint32_t a0 = sb + base + (j == 8 ? d.wB : d.wA), d1 = j == 8 ? 64 : 512, d2 = j == 8 ? 512 : 1024;
#pragma unroll
    for (int n = 0; n < 4; n++) {
        const uint32_t s2 = prmt(n < 2 ? s.x : s.y, 0, (n & 1) ? 0x3232 : 0x1010);
        uint32_t o0, o1, o2, o3;
        dq_quad(L, sel[n], m7c, s2, o0, o1);
        dq_quad(L, sel[4 + n], m7c, s2, o2, o3);
        sts128(a0 + (n & 1) * d1 + (n >> 1) * d2, o0, o1, o2, o3);
    }
    proxy_fence();
    __syncwarp();
    if (lead) {
        const uint32_t second = j == 8 ? HC : 1024, bar = OFF_WFULL + (c * 2 + ((j >> 2) & 1)) * 8, bar2 = bar + (j == 8 ? 8 : 0);
        bulk_s2s(pb + base, sb + base, 1024, pb + bar);
        bulk_s2s(pb + base + second, sb + base + second, 1024, pb + bar2);
        mbar_arrive(sb + bar); mbar_arrive(sb + bar2);
    }
}
__device__ __forceinline__ void lut_load(const void* lut, uint4& a, uint4& b) {
    asm volatile("ld.global.v4.u32 {%0,%1,%2,%3}, [%4];" : "=r"(a.x), "=r"(a.y), "=r"(a.z), "=r"(a.w) : "l"(lut) : "memory");
    asm volatile("ld.global.v4.u32 {%0,%1,%2,%3}, [%4+16];" : "=r"(b.x), "=r"(b.y), "=r"(b.z), "=r"(b.w) : "l"(lut) : "memory");
}
__device__ __forceinline__ void lut_split(const uint4& a, const uint4& b, Lut& L, uint32_t c16) {
    const uint32_t se = 0x6410 + c16, so = 0x7521 + c16;
    L.lo[0] = prmt(a.x, a.y, se); L.lo[1] = prmt(a.z, a.w, se); L.lo[2] = prmt(b.x, b.y, se); L.lo[3] = prmt(b.z, b.w, se);
    L.hi[0] = prmt(a.x, a.y, so); L.hi[1] = prmt(a.z, a.w, so); L.hi[2] = prmt(b.x, b.y, so); L.hi[3] = prmt(b.z, b.w, so);
    L.idn = 0x3210;
}

__global__ void __cluster_dims__(2, 1, 1) __launch_bounds__(512, 1)
nf4_gemm(const int* __restrict__ qw, const __nv_bfloat16* __restrict__ lut, const __nv_bfloat16* __restrict__ scales,
         __nv_bfloat16* __restrict__ out, const __nv_bfloat16* __restrict__ x,
         const __grid_constant__ CUtensorMap tmx, const __grid_constant__ CUtensorMap tmo) {
    extern __shared__ __align__(1024) uint8_t smem[];
    asm volatile("{\n.reg .pred p;\nsetp.lt.u32 p, %1, %2;\n@p prefetch.global.L2 [%0];\n}"
                 :: "l"((const char*)qw + (blockIdx.x * F_ + threadIdx.x * 128)), "r"(threadIdx.x), "n"(F_ / 128) : "memory");
    unsigned t_start; asm volatile("mov.u32 %0, %%clock;" : "=r"(t_start) :: "memory");
    constexpr unsigned long long HALF = 0xfe03f80ff00ff00aull;
    const unsigned long long upto = HALF << (63 - (blockIdx.x >> 1));
    const int half = upto >> 63, ones = __popcll(upto), slice = half ? ones - 1 : (blockIdx.x >> 1) - ones;
    const uint32_t rank = blockIdx.x & 1, row0 = (half * 2 + rank) * 512;
    const int col128 = slice * 128, col16 = 4096 + slice * 16;

    const uint32_t sb = __shfl_sync(0xffffffffu, smem_u32(smem), 0);
    const int warp = __reduce_max_sync(0xffffffffu, threadIdx.x >> 5), lane = threadIdx.x & 31;
    const char* lutp = (const char*)lut + ((threadIdx.x >> 10) << 4);
    uint32_t pb; asm("mapa.shared::cluster.u32 %0, %1, %2;" : "=r"(pb) : "r"(sb), "r"(rank ^ 1));
    const bool lead = elect();
    Dq dq;
    dq.qw = (const char*)qw; dq.sc = (const char*)scales;
    dq.qA = (lane >> 3) * 8 * (F_ * 4) + col128 * 4 + (lane & 7) * 16;
    dq.qB = (lane >> 2) * 8 * (F_ * 4) + col16 * 4 + (lane & 3) * 16;
    dq.sA = col128 * 2 + (lane & 7) * 8;
    dq.sB = (lane >> 4) * (F_ * 2) + col16 * 2 + (lane & 3) * 8;
    auto smem_offsets = [&](uint32_t l) {
        dq.wA = (l & 7) * 64 + (((l >> 3) ^ ((l >> 1) & 3)) * 16);
        dq.wB = (l >> 4) * HC + (l & 3) * 128 + ((((l >> 2) & 3) ^ (l & 3)) * 16);
    };

    if (warp < 8) {
        {
            Raw raw; uint2 sc; uint4 la, lb;
            const uint32_t u = warp * 2 + rank;
            if (warp >= 3) { cluster_arrive(); wait_until(t_start, kn.unit0 + (warp - 3) * kn.unit_step); }
            dq_load(dq, u, raw, sc); lut_load(lutp, la, lb);
            if (warp < 3) cluster_arrive();
            cluster_wait();
            Lut L;
            const uint32_t c16 = __shfl_sync(0xffffffffu, 16 + lane, 0);
            lut_split(la, lb, L, c16);
            smem_offsets(lane + c16 - 16);
            uint32_t sel[8]; dq_pack(raw, sel, c16);
            dq_store(dq, L, u, sel, sc, 0x7777, sb, pb, lead);
        }
        asm volatile("setmaxnreg.inc.sync.aligned.u32 176;");
        const int wg = warp >> 2, wq = warp & 3;
        float acc0[72], acc1[72];
        const uint32_t xlo = (((sb + OFF_X) >> 4) & 0x3fff) | (1u << 16), wlo = ((sb >> 4) & 0x3fff) | (1u << 16);
        auto release = [&](uint32_t slot) { if (lead) mbar_arrive(sb + OFF_EMPTY + slot * 8); };

        auto chunk = [&](auto first, uint32_t c) {
            const uint32_t s0 = (c & 1) * 4 + wg, s1 = s0 + 2, par = (c >> 1) & 1;
            const uint32_t a0 = xlo + s0 * (XS >> 4), a1 = a0 + 2 * (XS >> 4), b = wlo + c * (2 * HC >> 4);
            mbar_wait(sb + OFF_WFULL + c * 16, 0);
            mbar_wait(sb + OFF_FULL + s0 * 8, par);
            mma_half<first.value>(acc0, a0, b);
            if (!first.value) { wg_wait<1>(); release(s1 ^ 4); }
            mbar_wait(sb + OFF_FULL + s1 * 8, par);
            mma_half<first.value>(acc1, a1, b);
            mbar_wait(sb + OFF_WFULL + c * 16 + 8, 0);
            mma_half(acc0, a0 + 4, b + (HC >> 4));
            mma_half(acc1, a1 + 4, b + (HC >> 4));
            wg_wait<1>(); release(s0);
        };
        chunk(Bool<true>(), 0);
#pragma unroll 1
        for (uint32_t c = 1; c < NCH - 1; c++) chunk(Bool<false>(), c);
        {
            const uint32_t b = wlo + 8 * (2 * HC >> 4), a0 = xlo + wg * (XS >> 4);
            if (wg == 1) { wg_wait<0>(); release(7); bar_sync(1, 256); }
            mbar_wait(sb + OFF_WFULL + 16 * 8, 0);
            mbar_wait(sb + OFF_FULL + wg * 8, 0);
            mma_half(acc0, a0, b);
            wg_wait<1>(); if (wg == 0) release(6);
            mbar_wait(sb + OFF_WFULL + 17 * 8, 0);
            mma_half(acc0, a0 + 4, b + (HC >> 4));
            mbar_wait(sb + OFF_FULL + (wg + 2) * 8, 0);
            mma_step(acc1, a0 + 2 * (XS >> 4), b, 1);
            bar_arrive(wg == 0 ? 1 : 2, 256);
            wg_wait<1>(); release(wg);
        }
        if (warp == 0 && lead) asm volatile("mbarrier.arrive.shared::cluster.b64 _, [%0];" :: "r"(pb + OFF_DONE) : "memory");

        const uint32_t srow = (lane >> 3) + (lane & 4);
        const uint32_t stl = sb + OFF_STG + wq * 4096 + srow * 128 + (((lane & 3) ^ srow) * 16);
        char* const orow = (char*)out + (row0 + wg * 128 + wq * 16 + (lane >> 2)) * (F_ * 2);
        struct Half { uint32_t v[16]; };
        auto pack_half = [&](float (&d)[72], int h) {
            Half p;
#pragma unroll
            for (int J = 0; J < 4; J++) {
                const int b = 16 * J + 2 * h;
                p.v[4 * J] = pack_bf16(d[b], d[b + 4]); p.v[4 * J + 1] = pack_bf16(d[b + 8], d[b + 12]);
                p.v[4 * J + 2] = pack_bf16(d[b + 1], d[b + 5]); p.v[4 * J + 3] = pack_bf16(d[b + 9], d[b + 13]);
            }
            return p;
        };
        auto stage = [&](const Half& p, uint32_t n) {
            mbar_wait(sb + OFF_FREE + wq * 64 + (n & 7) * 8, n >> 3);
#pragma unroll
            for (int J = 0; J < 4; J++) sts128((stl ^ ((J & 1) * 64)) + (J >> 1) * 1024 + (n & 1) * 2048, p.v[4 * J], p.v[4 * J + 1], p.v[4 * J + 2], p.v[4 * J + 3]);
            if (n < 2) return;
            proxy_fence();
            __syncwarp();
            if (lead) mbar_arrive(sb + OFF_STAGED + wq * 16 + (n & 1) * 8);
        };
        auto piece = [&](float (&d)[72], int h, uint32_t n) { stage(pack_half(d, h), n); };
        auto pack_rest = [&](float (&d)[72]) { return make_uint4(pack_bf16(d[64], d[65]), pack_bf16(d[68], d[69]), pack_bf16(d[66], d[67]), pack_bf16(d[70], d[71])); };
        auto rest = [&](uint4 v, uint32_t rows) {
            char* p = orow + (col16 * 2 + (lane & 3) * 8);
            asm volatile("st.global.v2.u32 [%0], {%1, %2};" :: "l"(p + rows * (F_ * 2)), "r"(v.x), "r"(v.y) : "memory");
            asm volatile("st.global.v2.u32 [%0], {%1, %2};" :: "l"(p + (rows + 8) * (F_ * 2)), "r"(v.z), "r"(v.w) : "memory");
        };
        auto tile = [&](uint32_t h, bool last) {
            bar_sync(wg == 0 ? 2 : 1, 256);
            uint32_t prev = 0;
#pragma unroll 1
            for (int c = 0; c < NCH; c++, h++) {
                const uint32_t q = (h * 43u) >> 8, slot = h - q * 6;
                mbar_wait(sb + OFF_FULL + slot * 8, q & 1);
                mma_step(acc0, xlo + slot * (XS >> 4), wlo + c * (2 * HC >> 4), c);
                if (c == 8 && !last) bar_arrive(wg == 0 ? 1 : 2, 256);
                if (h == 4) { proxy_fence(); __syncwarp(); if (lead) { mbar_arrive(sb + OFF_STAGED + wq * 16); mbar_arrive(sb + OFF_STAGED + wq * 16 + 8); } }
                wg_wait<1>(); if (c > 0) release(prev);
                prev = slot;
            }
            wg_wait<0>(); release(prev);
            acc_fence(acc0);
        };

        acc_fence(acc0);
        if (wg == 0) piece(acc0, 0, 0);
        wg_wait<0>(); release(wg + 2);
        acc_fence(acc1);
        if (wg == 1) piece(acc0, 0, 2);
        piece(acc0, 1, 1 + 2 * wg);
        const uint4 rest0 = pack_rest(acc0);
        if (wg == 1) { rest(rest0, 0); piece(acc1, 0, 4); rest(pack_rest(acc1), 64); }

        tile(4 + wg * 9, false);
        if (wg == 0) { piece(acc1, 0, 5); piece(acc1, 1, 6); } else piece(acc1, 1, 8);
        piece(acc0, 0, 7 + 2 * wg);
        const Half late = pack_half(acc0, 1);
        if (wg == 1) stage(late, 10);
        rest(pack_rest(acc0), 256);
        if (wg == 0) rest(pack_rest(acc1), 64);

        tile(22 + wg * 9, wg == 1);
        if (wg == 0) { stage(late, 11); rest(rest0, 0); piece(acc0, 0, 12); piece(acc0, 1, 13); }
        else {
            char* p = orow + (320 * (F_ * 2) + col128 * 2 + (lane & 3) * 16);
#pragma unroll
            for (int h = 0; h < 2; h++) {
                const Half v = pack_half(acc0, h);
#pragma unroll
                for (int J = 0; J < 4; J++)
                    asm volatile("st.global.v4.u32 [%0], {%1, %2, %3, %4};" :: "l"(p + (h * (8 * F_ * 2) + J * 64)),
                                 "r"(v.v[4 * J]), "r"(v.v[4 * J + 1]), "r"(v.v[4 * J + 2]), "r"(v.v[4 * J + 3]) : "memory");
            }
        }
        rest(pack_rest(acc0), 320);
    } else {
        asm volatile("setmaxnreg.dec.sync.aligned.u32 80;");
        if (warp < 8 + NPW) {
            if (lead) {
                if (warp < 12) {
                    mbar_init(sb + OFF_STAGED + (warp - 8) * 16, 1); mbar_init(sb + OFF_STAGED + (warp - 8) * 16 + 8, 1);
#pragma unroll
                    for (int i = 0; i < 8; i++) mbar_init(sb + OFF_FREE + (warp - 8) * 64 + i * 8, 1);
                } else if (warp < 14) {
                    const uint32_t h = warp - 12, ev = h ? 4 : 6;
#pragma unroll
                    for (int c = 0; c < NCH; c++) mbar_init(sb + OFF_WFULL + c * 16 + h * 8, 1 + ((c & 1) == rank ? ev : 9 - ev));
#pragma unroll
                    for (int c = 0; c < NCH; c++) mbar_expect_tx(sb + OFF_WFULL + c * 16 + h * 8, ((c & 1) == rank ? 9 - ev : ev) * 1024);
                } else {
#pragma unroll
                    for (int i = 0; i < 8; i++) mbar_init(sb + OFF_EMPTY + i * 8, 4);
                    mbar_init(sb + OFF_DONE, 1);
                    mbar_init(sb + OFF_IDLE, 1);
                    asm volatile("prefetch.tensormap [%0];" :: "l"(&tmo) : "memory");
                }
                init_fence();
            }
            __syncwarp();
            cluster_arrive();
            Lut L; Raw codes; uint2 scA, scB; uint4 ta, tb;
            uint32_t u = warp * 2 + rank;
            wait_until(t_start, kn.unit0 + (warp - 3) * kn.unit_step + (warp > 8) * kn.unit_gap);
            lut_load(lutp, ta, tb);
            dq_load(dq, u, codes, scA);
            cluster_wait();
            lut_split(ta, tb, L, 15 + mbar_test(sb + OFF_IDLE, 1));
            smem_offsets(lane);
            auto round = [&](const uint2& cur, uint2& nxt) {
                uint32_t sel[8]; dq_pack(codes, sel, 16);
                const uint32_t un = u + 2 * NPW;
                if (un < NUNIT) dq_load(dq, un, codes, nxt);
                dq_store(dq, L, u, sel, cur, 0x7776 + mbar_test(sb + OFF_IDLE, 1), sb, pb, lead);
                u = un;
                return un < NUNIT;
            };
            scB = make_uint2(0, 0);
#pragma unroll 1
            while (round(scA, scB) && round(scB, scA)) {}

            if (warp < 12) {
                const int wq = warp - 8;
                bool pending = false;
#pragma unroll 1
                for (int n = 0; n < 14; n++) {
                    const uint32_t th = (0xba9dc783265410ull >> (4 * n)) & 15;
                    const int row = row0 + wq * 16 + (th >> 1) * 64 + (th & 1) * 8;
                    mbar_wait(sb + OFF_STAGED + wq * 16 + (n & 1) * 8, (n >> 1) & 1);
                    if (lead) {
                        asm volatile("cp.async.bulk.tensor.4d.global.shared::cta.bulk_group [%0, {%4, %3, %4, %2}], [%1];"
                                     :: "l"(&tmo), "r"(sb + OFF_STG + wq * 4096 + (n & 1) * 2048), "r"(slice * 2), "r"(row >> 1), "r"(0) : "memory");
                        asm volatile("cp.async.bulk.commit_group;" ::: "memory");
                        if (pending) {
                            asm volatile("cp.async.bulk.wait_group.read 1;" ::: "memory");
                            mbar_arrive(sb + OFF_FREE + wq * 64 + ((n + 1) & 7) * 8);
                        }
                    }
                    __syncwarp();
                    pending = __any_sync(0xffffffffu, mbar_test(sb + OFF_STAGED + wq * 16 + ((n + 1) & 1) * 8, ((n + 1) >> 1) & 1));
                    if (!pending && lead) {
                        asm volatile("cp.async.bulk.wait_group.read 0;" ::: "memory");
                        mbar_arrive(sb + OFF_FREE + wq * 64 + ((n + 2) & 7) * 8);
                    }
                    __syncwarp();
                }
            }
        } else {
            if (lead) {
                asm volatile("prefetch.tensormap [%0];" :: "l"(&tmx) : "memory");
#pragma unroll
                for (int i = 0; i < 8; i++) mbar_init(sb + OFF_FULL + i * 8, 1);
                init_fence();
            }
            __syncwarp();
            cluster_arrive();
            auto fill = [&](uint32_t slot, uint32_t k, uint32_t row) {
                if (lead) { mbar_expect_tx(sb + OFF_FULL + slot * 8, XS); tma2d(sb + OFF_X + slot * XS, &tmx, k, row, sb + OFF_FULL + slot * 8); }
            };
            auto row1 = [&](int i) { return row0 + ((i & 1) * 2 + ((i >> 1) & 1)) * 64; };
            wait_until(t_start, kn.x0);
#pragma unroll
            for (int i = 0; i < 4; i++) fill(i, 0, row1(i));
            wait_until(t_start, kn.x1);
#pragma unroll
            for (int i = 4; i < 8; i++) fill(i, 64, row1(i));
            cluster_wait();
#pragma unroll 1
            for (uint32_t q = 1; q < 4; q++) {
#pragma unroll
                for (int i = 0; i < 8; i++) {
                    mbar_wait(sb + OFF_EMPTY + i * 8, (q & 1) ^ 1);
                    fill(i, (q * 2 + (i >> 2)) * 64, row1(i));
                    if (i == 7 && q == 3 && lead)
                        asm volatile("cp.async.bulk.prefetch.L2.global [%0], %1;" :: "l"((const char*)x + (row0 + 256 + slice * 8) * (D_ * 2)), "r"(8 * D_ * 2) : "memory");
                }
            }
#pragma unroll
            for (int i = 0; i < 6; i++) {
                mbar_wait(sb + OFF_EMPTY + i * 8, 1);
                if (i < 4) fill(i, 8 * 64, row1(i)); else fill(i, (i - 4) * 64, row0 + 256);
            }
            mbar_wait(sb + OFF_EMPTY + 6 * 8, 1); mbar_wait(sb + OFF_EMPTY + 7 * 8, 1);
            if (lead) {
#pragma unroll
                for (int i = 0; i < 8; i++) mbar_arrive(sb + OFF_FREE + (i >> 1) * 64 + (i & 1) * 8);
            }
            uint32_t k = 2 * 64, row = row0 + 256, rstep = 128;
#pragma unroll 1
            for (uint32_t q = 1; q < 7; q++) {
#pragma unroll
                for (int i = 0; i < 6; i++) {
                    if (i < 4 || q < 6) {
                        mbar_wait(sb + OFF_EMPTY + i * 8, (q & 1) ^ 1);
                        fill(i, k, row);
                        k += 64;
                        if (k == D_) { k = 0; row += rstep; rstep = 64 - rstep; }
                    }
                }
            }
            mbar_wait(sb + OFF_DONE, 0);
        }
    }
}

typedef CUresult (*EncodeFn)(CUtensorMap*, CUtensorMapDataType, cuuint32_t, void*, const cuuint64_t*, const cuuint64_t*, const cuuint32_t*, const cuuint32_t*,
                             CUtensorMapInterleave, CUtensorMapSwizzle, CUtensorMapL2promotion, CUtensorMapFloatOOBfill);
}

extern "C" void kernel_launch(void* const* d_in, const int* in_sizes, int n_in, void* d_out, int out_size) {
    static EncodeFn enc = nullptr;
    if (!enc) {
        void* fn = nullptr; cudaDriverEntryPointQueryResult qr;
        cudaGetDriverEntryPoint("cuTensorMapEncodeTiled", &fn, cudaEnableDefault, &qr);
        enc = (EncodeFn)fn;
        cudaFuncSetAttribute(nf4_gemm, cudaFuncAttributeMaxDynamicSharedMemorySize, SMEM_BYTES);
    }
    CUtensorMap tmx, tmo;
    const cuuint32_t es[4] = {1, 1, 1, 1};
    {
        const cuuint64_t gd[2] = {D_, S_}, gs[1] = {D_ * 2}; const cuuint32_t box[2] = {64, 64};
        enc(&tmx, CU_TENSOR_MAP_DATA_TYPE_BFLOAT16, 2, d_in[0], gd, gs, box, es, CU_TENSOR_MAP_INTERLEAVE_NONE, CU_TENSOR_MAP_SWIZZLE_128B,
            CU_TENSOR_MAP_L2_PROMOTION_L2_128B, CU_TENSOR_MAP_FLOAT_OOB_FILL_NONE);
    }
    {
        const cuuint64_t gd[4] = {64, S_ / 2, 2, F_ / 64}, gs[3] = {F_ * 4, F_ * 2, 128}; const cuuint32_t box[4] = {64, 4, 2, 2};
        enc(&tmo, CU_TENSOR_MAP_DATA_TYPE_BFLOAT16, 4, d_out, gd, gs, box, es, CU_TENSOR_MAP_INTERLEAVE_NONE, CU_TENSOR_MAP_SWIZZLE_128B,
            CU_TENSOR_MAP_L2_PROMOTION_NONE, CU_TENSOR_MAP_FLOAT_OOB_FILL_NONE);
    }
    nf4_gemm<<<128, 512, SMEM_BYTES, cudaStreamPerThread>>>((const int*)d_in[1], (const __nv_bfloat16*)d_in[2], (const __nv_bfloat16*)d_in[3],
        (__nv_bfloat16*)d_out, (const __nv_bfloat16*)d_in[0], tmx, tmo);
}
```

```cpp
#include <cuda_runtime.h>
#include <cuda_bf16.h>
#include <cuda.h>
#include <stdint.h>

namespace {
constexpr int S_ = 2048, D_ = 576, F_ = 4608;
constexpr int BN = 144, NCH = 9;
constexpr int HC = BN * 64;
constexpr int XS = 8192;
constexpr int OFF_X = 2 * NCH * HC;
constexpr int OFF_STG = OFF_X + 6 * XS;
constexpr int OFF_BAR = OFF_X + 8 * XS;
constexpr int OFF_FULL = OFF_BAR, OFF_EMPTY = OFF_BAR + 64;
constexpr int OFF_STAGED = OFF_BAR + 128, OFF_FREE = OFF_BAR + 208;
constexpr int OFF_DONE = OFF_BAR + 192, OFF_IDLE = OFF_BAR + 200;
constexpr int OFF_WFULL = OFF_BAR + 464;
constexpr int SMEM_BYTES = OFF_BAR + 1024;
constexpr int NPW = 7;
constexpr int NUNIT = 9 * NCH;

struct Knobs { int unit0, unit_step, unit_gap, x0, x1; };
constexpr Knobs kn = {350, 190, 350, 800, 2150};

__device__ __forceinline__ uint32_t smem_u32(const void* p) { return (uint32_t)__cvta_generic_to_shared(p); }
__device__ __forceinline__ bool elect() { uint32_t p; asm volatile("{\n.reg .pred p;\nelect.sync _|p, 0xffffffff;\nselp.u32 %0, 1, 0, p;\n}" : "=r"(p)); return p; }
__device__ __forceinline__ void mbar_init(uint32_t bar, uint32_t cnt) { asm volatile("mbarrier.init.shared::cta.b64 [%0], %1;" :: "r"(bar), "r"(cnt) : "memory"); }
__device__ __forceinline__ void mbar_expect_tx(uint32_t bar, uint32_t bytes) { asm volatile("mbarrier.arrive.expect_tx.shared::cta.b64 _, [%0], %1;" :: "r"(bar), "r"(bytes) : "memory"); }
__device__ __forceinline__ void mbar_arrive(uint32_t bar) { asm volatile("mbarrier.arrive.shared::cta.b64 _, [%0];" :: "r"(bar) : "memory"); }
__device__ __forceinline__ void mbar_wait(uint32_t bar, uint32_t parity) {
    asm volatile("{\n.reg .pred p;\n.reg .u32 n;\n"
                 "mbarrier.try_wait.parity.shared::cta.b64 p, [%0], %1;\n@p bra.uni LAB_DONE;\nmov.u32 n, 0;\n"
                 "LAB_WAIT:\nmbarrier.try_wait.parity.shared::cta.b64 p, [%0], %1;\n@p bra.uni LAB_DONE;\n"
                 "add.u32 n, n, 1;\nsetp.lt.u32 p, n, 0x200000;\n@p bra.uni LAB_WAIT;\ntrap;\nLAB_DONE:\n}"
                 :: "r"(bar), "r"(parity) : "memory");
}
__device__ __forceinline__ uint32_t mbar_test(uint32_t bar, uint32_t parity) {
    uint32_t ok; asm volatile("{\n.reg .pred p;\nmbarrier.test_wait.parity.shared::cta.b64 p, [%1], %2;\nselp.u32 %0, 1, 0, p;\n}" : "=r"(ok) : "r"(bar), "r"(parity) : "memory");
    return ok;
}
__device__ __forceinline__ void tma2d(uint32_t dst, const CUtensorMap* tm, int c0, int c1, uint32_t bar) {
    asm volatile("cp.async.bulk.tensor.2d.shared::cluster.global.mbarrier::complete_tx::bytes [%0], [%1, {%3, %4}], [%2];"
                 :: "r"(dst), "l"(tm), "r"(bar), "r"(c0), "r"(c1) : "memory");
}
__device__ __forceinline__ void bulk_s2s(uint32_t dst, uint32_t src, uint32_t bytes, uint32_t bar) {
    asm volatile("cp.async.bulk.shared::cluster.shared::cta.mbarrier::complete_tx::bytes [%0], [%1], %2, [%3];" :: "r"(dst), "r"(src), "r"(bytes), "r"(bar) : "memory");
}
__device__ __forceinline__ void proxy_fence() { asm volatile("fence.proxy.async.shared::cta;" ::: "memory"); }
__device__ __forceinline__ void init_fence() { asm volatile("fence.mbarrier_init.release.cluster;" ::: "memory"); }
__device__ __forceinline__ void wg_fence() { asm volatile("wgmma.fence.sync.aligned;" ::: "memory"); }
__device__ __forceinline__ void wg_commit() { asm volatile("wgmma.commit_group.sync.aligned;" ::: "memory"); }
template <int N> __device__ __forceinline__ void wg_wait() { asm volatile("wgmma.wait_group.sync.aligned %0;" :: "n"(N) : "memory"); }
__device__ __forceinline__ void bar_sync(int id, int n) { asm volatile("bar.sync %0, %1;" :: "r"(id), "r"(n) : "memory"); }
__device__ __forceinline__ void bar_arrive(int id, int n) { asm volatile("bar.arrive %0, %1;" :: "r"(id), "r"(n) : "memory"); }
__device__ __forceinline__ void cluster_arrive() { asm volatile("barrier.cluster.arrive.relaxed.aligned;" ::: "memory"); }
__device__ __forceinline__ void cluster_wait() { asm volatile("barrier.cluster.wait.aligned;" ::: "memory"); }
__device__ __forceinline__ void wait_until(unsigned t0, unsigned dt) { unsigned now; do { asm volatile("mov.u32 %0, %%clock;" : "=r"(now)); } while (now - t0 < dt); }
__device__ __forceinline__ void sts128(uint32_t a, uint32_t v0, uint32_t v1, uint32_t v2, uint32_t v3) {
    asm volatile("st.shared.v4.u32 [%0], {%1, %2, %3, %4};" :: "r"(a), "r"(v0), "r"(v1), "r"(v2), "r"(v3) : "memory");
}

template <bool B> struct Bool { static constexpr bool value = B; };

constexpr uint32_t DESC_A = (1024u >> 4) | (1u << 30);
constexpr uint32_t DESC_B = (512u >> 4) | (2u << 30);
__device__ __forceinline__ uint64_t mk_desc(uint32_t lo, uint32_t hi) { uint64_t d; asm("mov.b64 %0, {%1, %2};" : "=l"(d) : "r"(lo), "r"(hi)); return d; }
#define ACC_REGS "%0, %1, %2, %3, %4, %5, %6, %7, %8, %9, %10, %11, %12, %13, %14, %15, %16, %17, %18, %19, %20, %21, %22, %23, " \
    "%24, %25, %26, %27, %28, %29, %30, %31, %32, %33, %34, %35, %36, %37, %38, %39, %40, %41, %42, %43, %44, %45, %46, %47, " \
    "%48, %49, %50, %51, %52, %53, %54, %55, %56, %57, %58, %59, %60, %61, %62, %63, %64, %65, %66, %67, %68, %69, %70, %71"
#define A8(d, o) "+f"(d[o]), "+f"(d[o + 1]), "+f"(d[o + 2]), "+f"(d[o + 3]), "+f"(d[o + 4]), "+f"(d[o + 5]), "+f"(d[o + 6]), "+f"(d[o + 7])
__device__ __forceinline__ void wgmma_n144(float (&d)[72], uint32_t a_lo, uint32_t b_lo, int scale_d) {
    asm volatile("{\n.reg .pred p;\nsetp.ne.b32 p, %74, 0;\n"
                 "wgmma.mma_async.sync.aligned.m64n144k16.f32.bf16.bf16 {" ACC_REGS "}, %72, %73, p, 1, 1, 0, 0;\n}\n"
                 : A8(d, 0), A8(d, 8), A8(d, 16), A8(d, 24), A8(d, 32), A8(d, 40), A8(d, 48), A8(d, 56), A8(d, 64)
                 : "l"(mk_desc(a_lo, DESC_A)), "l"(mk_desc(b_lo, DESC_B)), "r"(scale_d));
}
#define O8(d, o) "=f"(d[o]), "=f"(d[o + 1]), "=f"(d[o + 2]), "=f"(d[o + 3]), "=f"(d[o + 4]), "=f"(d[o + 5]), "=f"(d[o + 6]), "=f"(d[o + 7])
__device__ __forceinline__ void wgmma_n144_first(float (&d)[72], uint32_t a_lo, uint32_t b_lo) {
    asm volatile("wgmma.mma_async.sync.aligned.m64n144k16.f32.bf16.bf16 {" ACC_REGS "}, %72, %73, 0, 1, 1, 0, 0;\n"
                 : O8(d, 0), O8(d, 8), O8(d, 16), O8(d, 24), O8(d, 32), O8(d, 40), O8(d, 48), O8(d, 56), O8(d, 64)
                 : "l"(mk_desc(a_lo, DESC_A)), "l"(mk_desc(b_lo, DESC_B)));
}
__device__ __forceinline__ void acc_fence(float (&d)[72]) {
#pragma unroll
    for (int i = 0; i < 72; i++) asm volatile("" : "+f"(d[i]) :: "memory");
}
template <bool FIRST = false>
__device__ __forceinline__ void mma_half(float (&d)[72], uint32_t a_lo, uint32_t b_lo) {
    wg_fence();
    if (FIRST) wgmma_n144_first(d, a_lo, b_lo); else wgmma_n144(d, a_lo, b_lo, 1);
    wgmma_n144(d, a_lo + 2, b_lo + 2, 1);
    wg_commit();
}
__device__ __forceinline__ void mma_step(float (&d)[72], uint32_t a_lo, uint32_t b_lo, int accumulate) {
    wg_fence();
    wgmma_n144(d, a_lo, b_lo, accumulate);
    wgmma_n144(d, a_lo + 2, b_lo + 2, 1);
    wgmma_n144(d, a_lo + 4, b_lo + (HC >> 4), 1);
    wgmma_n144(d, a_lo + 6, b_lo + (HC >> 4) + 2, 1);
    wg_commit();
}
__device__ __forceinline__ uint32_t pack_bf16(float lo, float hi) {
    uint32_t r; asm("cvt.rn.bf16x2.f32 %0, %1, %2;" : "=r"(r) : "f"(hi), "f"(lo)); return r;
}

__device__ __forceinline__ uint32_t prmt(uint32_t a, uint32_t b, uint32_t c) { uint32_t r; asm("prmt.b32 %0, %1, %2, %3;" : "=r"(r) : "r"(a), "r"(b), "r"(c)); return r; }
__device__ __forceinline__ uint32_t hmul2(uint32_t a, uint32_t b) { uint32_t r; asm("mul.rn.bf16x2 %0, %1, %2;" : "=r"(r) : "r"(a), "r"(b)); return r; }
__device__ __forceinline__ uint32_t unit_kind(uint32_t pos) { return pos == 1 ? 8 : pos - (pos > 1); }
struct Raw { uint4 q[8]; };
struct Lut { uint32_t lo[4], hi[4], idn; };
struct Dq { const char* qw; const char* sc; uint32_t qA, qB, sA, sB, wA, wB; };
__device__ __forceinline__ void dq_load(const Dq& d, uint32_t u, Raw& r, uint2& s) {
    const uint32_t c = (u * 57u) >> 9, j = unit_kind(u - c * 9);
    const uint32_t g = c * 2 + ((j >> 2) & 1), cb = j & 3;
    const char* qp = d.qw + (g * (32 * F_ * 4) + cb * 128 + (j == 8 ? d.qB : d.qA));
#pragma unroll
    for (int i = 0; i < 8; i++)
        asm volatile("ld.global.L1::no_allocate.v4.u32 {%0,%1,%2,%3}, [%4];" : "=r"(r.q[i].x), "=r"(r.q[i].y), "=r"(r.q[i].z), "=r"(r.q[i].w) : "l"(qp + i * (F_ * 4)) : "memory");
    asm volatile("ld.global.v2.u32 {%0,%1}, [%2];" : "=r"(s.x), "=r"(s.y) : "l"(d.sc + (g * (F_ * 2) + cb * 64 + (j == 8 ? d.sB : d.sA))) : "memory");
}
__device__ __forceinline__ uint32_t pack4(uint32_t a, uint32_t b, uint32_t c, uint32_t d, uint32_t c16) {
    uint32_t r;
    asm volatile("{\n.reg .u32 t, u;\nmad.lo.u32 t, %2, %5, %1;\nmad.lo.u32 u, %4, %5, %3;\nmad.lo.u32 %0, u, 256, t;\n}" : "=r"(r) : "r"(a), "r"(b), "r"(c), "r"(d), "r"(c16));
    return r;
}
__device__ __forceinline__ void dq_pack(const Raw& r, uint32_t (&sel)[8], uint32_t c16) {
#pragma unroll
    for (int h = 0; h < 2; h++) {
        sel[h * 4 + 0] = pack4(r.q[4 * h].x, r.q[4 * h + 1].x, r.q[4 * h + 2].x, r.q[4 * h + 3].x, c16);
        sel[h * 4 + 1] = pack4(r.q[4 * h].y, r.q[4 * h + 1].y, r.q[4 * h + 2].y, r.q[4 * h + 3].y, c16);
        sel[h * 4 + 2] = pack4(r.q[4 * h].z, r.q[4 * h + 1].z, r.q[4 * h + 2].z, r.q[4 * h + 3].z, c16);
        sel[h * 4 + 3] = pack4(r.q[4 * h].w, r.q[4 * h + 1].w, r.q[4 * h + 2].w, r.q[4 * h + 3].w, c16);
    }
}
__device__ __forceinline__ void dq_quad(const Lut& L, uint32_t sel, uint32_t m7c, uint32_t s2, uint32_t& o0, uint32_t& o1) {
    uint32_t m7 = sel & m7c, pick;
    asm("lop3.b32 %0, %1, 0x4444, %2, 0xea;" : "=r"(pick) : "r"(sel >> 1), "r"(L.idn));
    const uint32_t lo = prmt(prmt(L.lo[0], L.lo[1], m7), prmt(L.lo[2], L.lo[3], m7), pick);
    const uint32_t hi = prmt(prmt(L.hi[0], L.hi[1], m7), prmt(L.hi[2], L.hi[3], m7), pick);
    o0 = hmul2(prmt(lo, hi, 0x5140), s2);
    o1 = hmul2(prmt(lo, hi, 0x7362), s2);
}
__device__ __forceinline__ void dq_store(const Dq& d, const Lut& L, uint32_t u, const uint32_t (&sel)[8], uint2 s, uint32_t m7c,
                                         uint32_t sb, uint32_t pb, bool lead) {
    const uint32_t c = (u * 57u) >> 9, j = unit_kind(u - c * 9);
    const uint32_t base = (c * 2 + ((j >> 2) & 1)) * HC + (j == 8 ? 8192 : (j & 3) * 2048);
    const uint32_t a0 = sb + base + (j == 8 ? d.wB : d.wA), d1 = j == 8 ? 64 : 512, d2 = j == 8 ? 512 : 1024;
#pragma unroll
    for (int n = 0; n < 4; n++) {
        const uint32_t s2 = prmt(n < 2 ? s.x : s.y, 0, (n & 1) ? 0x3232 : 0x1010);
        uint32_t o0, o1, o2, o3;
        dq_quad(L, sel[n], m7c, s2, o0, o1);
        dq_quad(L, sel[4 + n], m7c, s2, o2, o3);
        sts128(a0 + (n & 1) * d1 + (n >> 1) * d2, o0, o1, o2, o3);
    }
    proxy_fence();
    __syncwarp();
    if (lead) {
        const uint32_t second = j == 8 ? HC : 1024, bar = OFF_WFULL + (c * 2 + ((j >> 2) & 1)) * 8, bar2 = bar + (j == 8 ? 8 : 0);
        bulk_s2s(pb + base, sb + base, 1024, pb + bar);
        bulk_s2s(pb + base + second, sb + base + second, 1024, pb + bar2);
        mbar_arrive(sb + bar); mbar_arrive(sb + bar2);
    }
}
__device__ __forceinline__ void lut_load(const void* lut, uint4& a, uint4& b) {
    asm volatile("ld.global.v4.u32 {%0,%1,%2,%3}, [%4];" : "=r"(a.x), "=r"(a.y), "=r"(a.z), "=r"(a.w) : "l"(lut) : "memory");
    asm volatile("ld.global.v4.u32 {%0,%1,%2,%3}, [%4+16];" : "=r"(b.x), "=r"(b.y), "=r"(b.z), "=r"(b.w) : "l"(lut) : "memory");
}
__device__ __forceinline__ void lut_split(const uint4& a, const uint4& b, Lut& L, uint32_t c16) {
    const uint32_t se = 0x6410 + c16, so = 0x7521 + c16;
    L.lo[0] = prmt(a.x, a.y, se); L.lo[1] = prmt(a.z, a.w, se); L.lo[2] = prmt(b.x, b.y, se); L.lo[3] = prmt(b.z, b.w, se);
    L.hi[0] = prmt(a.x, a.y, so); L.hi[1] = prmt(a.z, a.w, so); L.hi[2] = prmt(b.x, b.y, so); L.hi[3] = prmt(b.z, b.w, so);
    L.idn = 0x3210;
}

__global__ void __cluster_dims__(2, 1, 1) __launch_bounds__(512, 1)
nf4_gemm(const int* __restrict__ qw, const __nv_bfloat16* __restrict__ lut, const __nv_bfloat16* __restrict__ scales,
         __nv_bfloat16* __restrict__ out, const __nv_bfloat16* __restrict__ x,
         const __grid_constant__ CUtensorMap tmx, const __grid_constant__ CUtensorMap tmo) {
    extern __shared__ __align__(1024) uint8_t smem[];
    asm volatile("{\n.reg .pred p;\nsetp.lt.u32 p, %1, %2;\n@p prefetch.global.L2 [%0];\n}"
                 :: "l"((const char*)qw + (blockIdx.x * F_ + threadIdx.x * 128)), "r"(threadIdx.x), "n"(F_ / 128) : "memory");
    unsigned t_start; asm volatile("mov.u32 %0, %%clock;" : "=r"(t_start) :: "memory");
    constexpr unsigned long long HALF = 0xfe03f80ff00ff00aull;
    const unsigned long long upto = HALF << (63 - (blockIdx.x >> 1));
    const int half = upto >> 63, ones = __popcll(upto), slice = half ? ones - 1 : (blockIdx.x >> 1) - ones;
    const uint32_t rank = blockIdx.x & 1, row0 = (half * 2 + rank) * 512;
    const int col128 = slice * 128, col16 = 4096 + slice * 16;

    const uint32_t sb = __shfl_sync(0xffffffffu, smem_u32(smem), 0);
    const int warp = __reduce_max_sync(0xffffffffu, threadIdx.x >> 5), lane = threadIdx.x & 31;
    const char* lutp = (const char*)lut + ((threadIdx.x >> 10) << 4);
    uint32_t pb; asm("mapa.shared::cluster.u32 %0, %1, %2;" : "=r"(pb) : "r"(sb), "r"(rank ^ 1));
    const bool lead = elect();
    Dq dq;
    dq.qw = (const char*)qw; dq.sc = (const char*)scales;
    dq.qA = (lane >> 3) * 8 * (F_ * 4) + col128 * 4 + (lane & 7) * 16;
    dq.qB = (lane >> 2) * 8 * (F_ * 4) + col16 * 4 + (lane & 3) * 16;
    dq.sA = col128 * 2 + (lane & 7) * 8;
    dq.sB = (lane >> 4) * (F_ * 2) + col16 * 2 + (lane & 3) * 8;
    dq.wA = (lane & 7) * 64 + (((lane >> 3) ^ ((lane >> 1) & 3)) * 16);
    dq.wB = (lane >> 4) * HC + (lane & 3) * 128 + ((((lane >> 2) & 3) ^ (lane & 3)) * 16);

    if (warp < 8) {
        {
            Raw raw; uint2 sc; uint4 la, lb;
            const uint32_t u = warp * 2 + rank;
            if (warp >= 3) { cluster_arrive(); wait_until(t_start, kn.unit0 + (warp - 3) * kn.unit_step); }
            dq_load(dq, u, raw, sc); lut_load(lutp, la, lb);
            if (warp < 3) cluster_arrive();
            cluster_wait();
            Lut L;
            const uint32_t c16 = __shfl_sync(0xffffffffu, 16 + lane, 0);
            lut_split(la, lb, L, c16);
            uint32_t sel[8]; dq_pack(raw, sel, c16);
            dq_store(dq, L, u, sel, sc, 0x7777, sb, pb, lead);
        }
        asm volatile("setmaxnreg.inc.sync.aligned.u32 176;");
        const int wg = warp >> 2, wq = warp & 3;
        float acc0[72], acc1[72];
        const uint32_t xlo = (((sb + OFF_X) >> 4) & 0x3fff) | (1u << 16), wlo = ((sb >> 4) & 0x3fff) | (1u << 16);
        auto release = [&](uint32_t slot) { if (lead) mbar_arrive(sb + OFF_EMPTY + slot * 8); };

        auto chunk = [&](auto first, uint32_t c) {
            const uint32_t s0 = (c & 1) * 4 + wg, s1 = s0 + 2, par = (c >> 1) & 1;
            const uint32_t a0 = xlo + s0 * (XS >> 4), a1 = a0 + 2 * (XS >> 4), b = wlo + c * (2 * HC >> 4);
            mbar_wait(sb + OFF_WFULL + c * 16, 0);
            mbar_wait(sb + OFF_FULL + s0 * 8, par);
            mma_half<first.value>(acc0, a0, b);
            if (!first.value) { wg_wait<1>(); release(s1 ^ 4); }
            mbar_wait(sb + OFF_FULL + s1 * 8, par);
            mma_half<first.value>(acc1, a1, b);
            mbar_wait(sb + OFF_WFULL + c * 16 + 8, 0);
            mma_half(acc0, a0 + 4, b + (HC >> 4));
            mma_half(acc1, a1 + 4, b + (HC >> 4));
            wg_wait<1>(); release(s0);
        };
        chunk(Bool<true>(), 0);
#pragma unroll 1
        for (uint32_t c = 1; c < NCH - 1; c++) chunk(Bool<false>(), c);
        {
            const uint32_t b = wlo + 8 * (2 * HC >> 4), a0 = xlo + wg * (XS >> 4);
            if (wg == 1) { wg_wait<0>(); release(7); bar_sync(1, 256); }
            mbar_wait(sb + OFF_WFULL + 16 * 8, 0);
            mbar_wait(sb + OFF_FULL + wg * 8, 0);
            mma_half(acc0, a0, b);
            wg_wait<1>(); if (wg == 0) release(6);
            mbar_wait(sb + OFF_WFULL + 17 * 8, 0);
            mma_half(acc0, a0 + 4, b + (HC >> 4));
            mbar_wait(sb + OFF_FULL + (wg + 2) * 8, 0);
            mma_step(acc1, a0 + 2 * (XS >> 4), b, 1);
            bar_arrive(wg == 0 ? 1 : 2, 256);
            wg_wait<1>(); release(wg);
        }
        if (warp == 0 && lead) asm volatile("mbarrier.arrive.shared::cluster.b64 _, [%0];" :: "r"(pb + OFF_DONE) : "memory");

        const uint32_t srow = (lane >> 3) + (lane & 4);
        const uint32_t stl = sb + OFF_STG + wq * 4096 + srow * 128 + (((lane & 3) ^ srow) * 16);
        char* const orow = (char*)out + (row0 + wg * 128 + wq * 16 + (lane >> 2)) * (F_ * 2);
        struct Half { uint32_t v[16]; };
        auto pack_half = [&](float (&d)[72], int h) {
            Half p;
#pragma unroll
            for (int J = 0; J < 4; J++) {
                const int b = 16 * J + 2 * h;
                p.v[4 * J] = pack_bf16(d[b], d[b + 4]); p.v[4 * J + 1] = pack_bf16(d[b + 8], d[b + 12]);
                p.v[4 * J + 2] = pack_bf16(d[b + 1], d[b + 5]); p.v[4 * J + 3] = pack_bf16(d[b + 9], d[b + 13]);
            }
            return p;
        };
        auto stage = [&](const Half& p, uint32_t n) {
            mbar_wait(sb + OFF_FREE + wq * 64 + (n & 7) * 8, n >> 3);
#pragma unroll
            for (int J = 0; J < 4; J++) sts128((stl ^ ((J & 1) * 64)) + (J >> 1) * 1024 + (n & 1) * 2048, p.v[4 * J], p.v[4 * J + 1], p.v[4 * J + 2], p.v[4 * J + 3]);
            if (n < 2) return;
            proxy_fence();
            __syncwarp();
            if (lead) mbar_arrive(sb + OFF_STAGED + wq * 16 + (n & 1) * 8);
        };
        auto piece = [&](float (&d)[72], int h, uint32_t n) { stage(pack_half(d, h), n); };
        auto pack_rest = [&](float (&d)[72]) { return make_uint4(pack_bf16(d[64], d[65]), pack_bf16(d[68], d[69]), pack_bf16(d[66], d[67]), pack_bf16(d[70], d[71])); };
        auto rest = [&](uint4 v, uint32_t rows) {
            char* p = orow + (col16 * 2 + (lane & 3) * 8);
            asm volatile("st.global.v2.u32 [%0], {%1, %2};" :: "l"(p + rows * (F_ * 2)), "r"(v.x), "r"(v.y) : "memory");
            asm volatile("st.global.v2.u32 [%0], {%1, %2};" :: "l"(p + (rows + 8) * (F_ * 2)), "r"(v.z), "r"(v.w) : "memory");
        };
        auto tile = [&](uint32_t h, bool last) {
            bar_sync(wg == 0 ? 2 : 1, 256);
            uint32_t prev = 0;
#pragma unroll 1
            for (int c = 0; c < NCH; c++, h++) {
                const uint32_t q = (h * 43u) >> 8, slot = h - q * 6;
                mbar_wait(sb + OFF_FULL + slot * 8, q & 1);
                mma_step(acc0, xlo + slot * (XS >> 4), wlo + c * (2 * HC >> 4), c);
                if (c == 8 && !last) bar_arrive(wg == 0 ? 1 : 2, 256);
                if (h == 4) { proxy_fence(); __syncwarp(); if (lead) { mbar_arrive(sb + OFF_STAGED + wq * 16); mbar_arrive(sb + OFF_STAGED + wq * 16 + 8); } }
                wg_wait<1>(); if (c > 0) release(prev);
                prev = slot;
            }
            wg_wait<0>(); release(prev);
            acc_fence(acc0);
        };

        acc_fence(acc0);
        if (wg == 0) piece(acc0, 0, 0);
        wg_wait<0>(); release(wg + 2);
        acc_fence(acc1);
        if (wg == 1) piece(acc0, 0, 2);
        piece(acc0, 1, 1 + 2 * wg);
        const uint4 rest0 = pack_rest(acc0);
        if (wg == 1) { rest(rest0, 0); piece(acc1, 0, 4); rest(pack_rest(acc1), 64); }

        tile(4 + wg * 9, false);
        if (wg == 0) { piece(acc1, 0, 5); piece(acc1, 1, 6); } else piece(acc1, 1, 8);
        piece(acc0, 0, 7 + 2 * wg);
        const Half late = pack_half(acc0, 1);
        if (wg == 1) stage(late, 10);
        rest(pack_rest(acc0), 256);
        if (wg == 0) rest(pack_rest(acc1), 64);

        tile(22 + wg * 9, wg == 1);
        if (wg == 0) { stage(late, 11); rest(rest0, 0); piece(acc0, 0, 12); piece(acc0, 1, 13); rest(pack_rest(acc0), 320); }
        else {
            rest(pack_rest(acc0), 320);
            char* p = orow + (320 * (F_ * 2) + col128 * 2 + (lane & 3) * 16);
#pragma unroll
            for (int h = 0; h < 2; h++) {
                const Half v = pack_half(acc0, h);
#pragma unroll
                for (int J = 0; J < 4; J++)
                    asm volatile("st.global.v4.u32 [%0], {%1, %2, %3, %4};" :: "l"(p + (h * (8 * F_ * 2) + J * 64)),
                                 "r"(v.v[4 * J]), "r"(v.v[4 * J + 1]), "r"(v.v[4 * J + 2]), "r"(v.v[4 * J + 3]) : "memory");
            }
        }
    } else {
        asm volatile("setmaxnreg.dec.sync.aligned.u32 80;");
        if (warp < 8 + NPW) {
            if (lead) {
                if (warp < 12) {
                    mbar_init(sb + OFF_STAGED + (warp - 8) * 16, 1); mbar_init(sb + OFF_STAGED + (warp - 8) * 16 + 8, 1);
#pragma unroll
                    for (int i = 0; i < 8; i++) mbar_init(sb + OFF_FREE + (warp - 8) * 64 + i * 8, 1);
                } else if (warp < 14) {
                    const uint32_t h = warp - 12, ev = h ? 4 : 6;
#pragma unroll
                    for (int c = 0; c < NCH; c++) mbar_init(sb + OFF_WFULL + c * 16 + h * 8, 1 + ((c & 1) == rank ? ev : 9 - ev));
#pragma unroll
                    for (int c = 0; c < NCH; c++) mbar_expect_tx(sb + OFF_WFULL + c * 16 + h * 8, ((c & 1) == rank ? 9 - ev : ev) * 1024);
                } else {
#pragma unroll
                    for (int i = 0; i < 8; i++) mbar_init(sb + OFF_EMPTY + i * 8, 4);
                    mbar_init(sb + OFF_DONE, 1);
                    mbar_init(sb + OFF_IDLE, 1);
                    asm volatile("prefetch.tensormap [%0];" :: "l"(&tmo) : "memory");
                }
                init_fence();
            }
            __syncwarp();
            cluster_arrive();
            Lut L; Raw codes; uint2 scA, scB; uint4 ta, tb;
            uint32_t u = warp * 2 + rank;
            wait_until(t_start, kn.unit0 + (warp - 3) * kn.unit_step + (warp > 8) * kn.unit_gap);
            lut_load(lutp, ta, tb);
            dq_load(dq, u, codes, scA);
            cluster_wait();
            lut_split(ta, tb, L, 15 + mbar_test(sb + OFF_IDLE, 1));
            auto round = [&](const uint2& cur, uint2& nxt) {
                uint32_t sel[8]; dq_pack(codes, sel, 16);
                const uint32_t un = u + 2 * NPW;
                if (un < NUNIT) dq_load(dq, un, codes, nxt);
                dq_store(dq, L, u, sel, cur, 0x7776 + mbar_test(sb + OFF_IDLE, 1), sb, pb, lead);
                u = un;
                return un < NUNIT;
            };
            scB = make_uint2(0, 0);
#pragma unroll 1
            while (round(scA, scB) && round(scB, scA)) {}

            if (warp < 12) {
                const int wq = warp - 8;
                bool pending = false;
#pragma unroll 1
                for (int n = 0; n < 14; n++) {
                    const uint32_t th = (0xba9dc783265410ull >> (4 * n)) & 15;
                    const int row = row0 + wq * 16 + (th >> 1) * 64 + (th & 1) * 8;
                    mbar_wait(sb + OFF_STAGED + wq * 16 + (n & 1) * 8, (n >> 1) & 1);
                    if (lead) {
                        asm volatile("cp.async.bulk.tensor.4d.global.shared::cta.bulk_group [%0, {%4, %3, %4, %2}], [%1];"
                                     :: "l"(&tmo), "r"(sb + OFF_STG + wq * 4096 + (n & 1) * 2048), "r"(slice * 2), "r"(row >> 1), "r"(0) : "memory");
                        asm volatile("cp.async.bulk.commit_group;" ::: "memory");
                        if (pending) {
                            asm volatile("cp.async.bulk.wait_group.read 1;" ::: "memory");
                            mbar_arrive(sb + OFF_FREE + wq * 64 + ((n + 1) & 7) * 8);
                        }
                    }
                    __syncwarp();
                    pending = __any_sync(0xffffffffu, mbar_test(sb + OFF_STAGED + wq * 16 + ((n + 1) & 1) * 8, ((n + 1) >> 1) & 1));
                    if (!pending && lead) {
                        asm volatile("cp.async.bulk.wait_group.read 0;" ::: "memory");
                        mbar_arrive(sb + OFF_FREE + wq * 64 + ((n + 2) & 7) * 8);
                    }
                    __syncwarp();
                }
            }
        } else {
            if (lead) {
                asm volatile("prefetch.tensormap [%0];" :: "l"(&tmx) : "memory");
#pragma unroll
                for (int i = 0; i < 8; i++) mbar_init(sb + OFF_FULL + i * 8, 1);
                init_fence();
            }
            __syncwarp();
            cluster_arrive();
            auto fill = [&](uint32_t slot, uint32_t k, uint32_t row) {
                if (lead) { mbar_expect_tx(sb + OFF_FULL + slot * 8, XS); tma2d(sb + OFF_X + slot * XS, &tmx, k, row, sb + OFF_FULL + slot * 8); }
            };
            auto row1 = [&](int i) { return row0 + ((i & 1) * 2 + ((i >> 1) & 1)) * 64; };
            wait_until(t_start, kn.x0);
#pragma unroll
            for (int i = 0; i < 4; i++) fill(i, 0, row1(i));
            wait_until(t_start, kn.x1);
#pragma unroll
            for (int i = 4; i < 8; i++) fill(i, 64, row1(i));
            cluster_wait();
#pragma unroll 1
            for (uint32_t q = 1; q < 4; q++) {
#pragma unroll
                for (int i = 0; i < 8; i++) {
                    mbar_wait(sb + OFF_EMPTY + i * 8, (q & 1) ^ 1);
                    fill(i, (q * 2 + (i >> 2)) * 64, row1(i));
                    if (i == 7 && q == 3 && lead)
                        asm volatile("cp.async.bulk.prefetch.L2.global [%0], %1;" :: "l"((const char*)x + (row0 + 256 + slice * 8) * (D_ * 2)), "r"(8 * D_ * 2) : "memory");
                }
            }
#pragma unroll
            for (int i = 0; i < 6; i++) {
                mbar_wait(sb + OFF_EMPTY + i * 8, 1);
                if (i < 4) fill(i, 8 * 64, row1(i)); else fill(i, (i - 4) * 64, row0 + 256);
            }
            mbar_wait(sb + OFF_EMPTY + 6 * 8, 1); mbar_wait(sb + OFF_EMPTY + 7 * 8, 1);
            if (lead) {
#pragma unroll
                for (int i = 0; i < 8; i++) mbar_arrive(sb + OFF_FREE + (i >> 1) * 64 + (i & 1) * 8);
            }
            uint32_t k = 2 * 64, row = row0 + 256, rstep = 128;
#pragma unroll 1
            for (uint32_t q = 1; q < 7; q++) {
#pragma unroll
                for (int i = 0; i < 6; i++) {
                    if (i < 4 || q < 6) {
                        mbar_wait(sb + OFF_EMPTY + i * 8, (q & 1) ^ 1);
                        fill(i, k, row);
                        k += 64;
                        if (k == D_) { k = 0; row += rstep; rstep = 64 - rstep; }
                    }
                }
            }
            mbar_wait(sb + OFF_DONE, 0);
        }
    }
}

typedef CUresult (*EncodeFn)(CUtensorMap*, CUtensorMapDataType, cuuint32_t, void*, const cuuint64_t*, const cuuint64_t*, const cuuint32_t*, const cuuint32_t*,
                             CUtensorMapInterleave, CUtensorMapSwizzle, CUtensorMapL2promotion, CUtensorMapFloatOOBfill);
}

extern "C" void kernel_launch(void* const* d_in, const int* in_sizes, int n_in, void* d_out, int out_size) {
    static EncodeFn enc = nullptr;
    if (!enc) {
        void* fn = nullptr; cudaDriverEntryPointQueryResult qr;
        cudaGetDriverEntryPoint("cuTensorMapEncodeTiled", &fn, cudaEnableDefault, &qr);
        enc = (EncodeFn)fn;
        cudaFuncSetAttribute(nf4_gemm, cudaFuncAttributeMaxDynamicSharedMemorySize, SMEM_BYTES);
    }
    CUtensorMap tmx, tmo;
    const cuuint32_t es[4] = {1, 1, 1, 1};
    {
        const cuuint64_t gd[2] = {D_, S_}, gs[1] = {D_ * 2}; const cuuint32_t box[2] = {64, 64};
        enc(&tmx, CU_TENSOR_MAP_DATA_TYPE_BFLOAT16, 2, d_in[0], gd, gs, box, es, CU_TENSOR_MAP_INTERLEAVE_NONE, CU_TENSOR_MAP_SWIZZLE_128B,
            CU_TENSOR_MAP_L2_PROMOTION_L2_128B, CU_TENSOR_MAP_FLOAT_OOB_FILL_NONE);
    }
    {
        const cuuint64_t gd[4] = {64, S_ / 2, 2, F_ / 64}, gs[3] = {F_ * 4, F_ * 2, 128}; const cuuint32_t box[4] = {64, 4, 2, 2};
        enc(&tmo, CU_TENSOR_MAP_DATA_TYPE_BFLOAT16, 4, d_out, gd, gs, box, es, CU_TENSOR_MAP_INTERLEAVE_NONE, CU_TENSOR_MAP_SWIZZLE_128B,
            CU_TENSOR_MAP_L2_PROMOTION_NONE, CU_TENSOR_MAP_FLOAT_OOB_FILL_NONE);
    }
    nf4_gemm<<<128, 512, SMEM_BYTES, cudaStreamPerThread>>>((const int*)d_in[1], (const __nv_bfloat16*)d_in[2], (const __nv_bfloat16*)d_in[3],
        (__nv_bfloat16*)d_out, (const __nv_bfloat16*)d_in[0], tmx, tmo);
}
```
